```python
import torch

def _softmax(x, axis=-1):
    return torch.softmax(x, dim=axis)
def _gelu(x):
    return torch.nn.functional.gelu(x, approximate="tanh")
def _silu(x):
    return torch.nn.functional.silu(x)
def _sigmoid(x):
    return torch.sigmoid(x)
def _layernorm(x, axis=-1, eps=1e-5):
    m = x.mean(dim=axis, keepdim=True)
    v = x.var(dim=axis, keepdim=True, unbiased=False)
    return (x - m) / torch.sqrt(v + eps)
def _scatter_add(tgt, idx, src, axis=0):
    return tgt.clone().index_add_(axis, idx, src)
def _segment_sum(src, seg, n):
    out = torch.zeros((n,) + src.shape[1:], dtype=src.dtype)
    return out.index_add_(0, seg, src)
def _pad(x, pw):
    flat = tuple(v for pair in reversed(pw) for v in pair)
    return torch.nn.functional.pad(x, flat)

kernel_name = 'standalone__kv_cache_quant_int4_int2_kv_with_per_channel_or_per_token_scales__decode'

def setup_inputs():

    _w = (lambda a: (lambda t: t.to(torch.bfloat16) if t.is_floating_point() else t)(torch.as_tensor(a)))
    B = 1
    Sq = 1
    Skv = 65536
    Hq = 32
    Hkv = 16
    Dh = 128
    bits = 4
    G = -1
    if G <= 0 or G >= Skv:
        G = max(1, Skv // 2)
    Skv = (Skv // G) * G
    ngk = Skv // G
    qmax = (1 << bits) - 1
    return {
        "q": _w((lambda *s: torch.randn(*s, dtype=torch.bfloat16) * 1.6)(B, Hq, Sq, Dh)),
        "qk": _w(torch.randint(0, qmax + 1, (B, Hkv, Skv, Dh)).to(torch.int32)),
        "qv": _w(torch.randint(0, qmax + 1, (B, Hkv, Skv, Dh)).to(torch.int32)),
        "k_scales": _w(torch.abs((lambda *s: torch.randn(*s, dtype=torch.bfloat16) * 1.6)(B, Hkv, ngk, Dh)) * 0.05 + 0.02),
        "k_zeros": _w((lambda *s: torch.randn(*s, dtype=torch.bfloat16) * 1.6)(B, Hkv, ngk, Dh) + float(qmax) / 2.0),
        "v_scales": _w(torch.abs((lambda *s: torch.randn(*s, dtype=torch.bfloat16) * 0.05)(B, Hkv, Skv, 1)) * 0.05 + 0.02),
        "v_zeros": _w((lambda *s: torch.randn(*s, dtype=torch.bfloat16) * 0.05)(B, Hkv, Skv, 1) + float(qmax) / 2.0),
    }

def reference(q, qk, qv, k_scales, k_zeros, v_scales, v_zeros):
    B, Hq, Sq, Dh = q.shape
    Hkv, Skv = qk.shape[1], qk.shape[2]
    ngk = k_scales.shape[2]
    G = Skv // ngk
    ks = (lambda x, n, axis: torch.repeat_interleave(x, n, dim=axis))(k_scales, G, axis=2)
    kz = (lambda x, n, axis: torch.repeat_interleave(x, n, dim=axis))(k_zeros, G, axis=2)
    k = ((lambda x, dt: x.to(dt))(qk, q.dtype) - kz) * ks
    v = ((lambda x, dt: x.to(dt))(qv, q.dtype) - v_zeros) * v_scales
    rep = Hq // Hkv
    if rep > 1:
        k = (lambda x, n, axis: torch.repeat_interleave(x, n, dim=axis))(k, rep, axis=1)
        v = (lambda x, n, axis: torch.repeat_interleave(x, n, dim=axis))(v, rep, axis=1)
    scale = float(Dh) ** -0.5
    logits = torch.einsum("bhqd,bhkd->bhqk", q, k) * scale
    p = _softmax(logits, axis=-1)
    o = torch.einsum("bhqk,bhkd->bhqd", p, v)
    return o
```

```cpp
#include <cuda_runtime.h>
#include <cuda_bf16.h>
#include <stdint.h>

namespace kvq {

constexpr int HKV = 16, SKV = 65536, DH = 128, REP = 2, NGK = 2;
constexpr int HQ = HKV * REP;
constexpr int GROUP = SKV / NGK;
constexpr int TT = 32;
constexpr int TILE_BYTES = TT * DH * 4;
constexpr int NST = 4;
constexpr int CW = 8;
constexpr int NCT = CW * 32;
constexpr int NTILES = HKV * SKV / TT;
constexpr int TILES_PER_GROUP = GROUP / TT;
constexpr int MAXG = 160;
constexpr int NCOLB = HQ * 4;

__device__ unsigned int g_ctr;
__device__ unsigned int g_epoch;
__device__ ulonglong2 g_part[HQ][MAXG][DH / 2];
__device__ unsigned long long g_lse[HQ][MAXG];

struct __align__(128) Smem {
    int4 kv[NST][2][TT * DH / 4];
    uint16_t vs[NST][TT];
    uint16_t vz[NST][TT];
    uint16_t q[HQ * DH];
    uint16_t ks[HKV * NGK * DH];
    uint16_t kz[HKV * NGK * DH];
    float wacc[CW][REP][DH];
    float wm[CW][REP];
    float wl[CW][REP];
    float4 fin[CW][16];
    unsigned long long fullK[NST], fullV[NST], empty[NST], parbar;
    int tile[NST];
    unsigned int epoch;
};

__device__ __forceinline__ uint32_t smem_u32(const void* p) { return (uint32_t)__cvta_generic_to_shared(p); }
__device__ __forceinline__ void mbar_init(uint32_t bar, int cnt) {
    asm volatile("mbarrier.init.shared::cta.b64 [%0], %1;" ::"r"(bar), "r"(cnt) : "memory");
}
__device__ __forceinline__ void mbar_expect_tx(uint32_t bar, uint32_t bytes) {
    asm volatile("mbarrier.arrive.expect_tx.shared::cta.b64 _, [%0], %1;" ::"r"(bar), "r"(bytes) : "memory");
}
__device__ __forceinline__ void mbar_arrive(uint32_t bar) {
    asm volatile("mbarrier.arrive.shared::cta.b64 _, [%0];" ::"r"(bar) : "memory");
}
__device__ __forceinline__ bool mbar_try(uint32_t bar, uint32_t parity) {
    uint32_t ok;
    asm volatile(
        "{\n.reg .pred p;\n"
        "mbarrier.try_wait.parity.shared::cta.b64 p, [%1], %2;\n"
        "selp.u32 %0, 1, 0, p;\n}"
        : "=r"(ok) : "r"(bar), "r"(parity) : "memory");
    return ok != 0;
}
__device__ __forceinline__ void mbar_wait(uint32_t bar, uint32_t parity) {
    if (mbar_try(bar, parity)) return;
    for (uint32_t it = 0; it < (1u << 24); ++it)
        if (mbar_try(bar, parity)) return;
    __trap();
}
__device__ __forceinline__ void bulk_load(uint32_t dst, const void* src, uint32_t bytes, uint32_t bar, uint64_t pol) {
    asm volatile(
        "cp.async.bulk.shared::cluster.global.mbarrier::complete_tx::bytes.L2::cache_hint [%0], [%1], %2, [%3], %4;"
        ::"r"(dst), "l"(src), "r"(bytes), "r"(bar), "l"(pol) : "memory");
}
__device__ __forceinline__ void bulk_load_nohint(uint32_t dst, const void* src, uint32_t bytes, uint32_t bar) {
    asm volatile(
        "cp.async.bulk.shared::cluster.global.mbarrier::complete_tx::bytes [%0], [%1], %2, [%3];"
        ::"r"(dst), "l"(src), "r"(bytes), "r"(bar) : "memory");
}
__device__ __forceinline__ float ex2(float x) {
    float y;
    asm("ex2.approx.ftz.f32 %0, %1;" : "=f"(y) : "f"(x));
    return y;
}
__device__ __forceinline__ float bf2f(uint32_t lo16) { return __uint_as_float(lo16 << 16); }
__device__ __forceinline__ void cons_sync() { asm volatile("bar.sync 1, %0;" ::"n"(NCT) : "memory"); }
__device__ __forceinline__ unsigned long long pack_tag(float v, uint32_t tag) {
    return ((unsigned long long)tag << 32) | (unsigned long long)__float_as_uint(v);
}
__device__ __forceinline__ void st_relaxed_u64(unsigned long long* p, unsigned long long v) {
    asm volatile("st.relaxed.gpu.global.b64 [%0], %1;" ::"l"(p), "l"(v) : "memory");
}
__device__ __forceinline__ unsigned long long ld_relaxed_u64(const unsigned long long* p) {
    unsigned long long v;
    asm volatile("ld.relaxed.gpu.global.b64 %0, [%1];" : "=l"(v) : "l"(p) : "memory");
    return v;
}
__device__ __forceinline__ ulonglong2 ld_relaxed_v2u64(const ulonglong2* p) {
    ulonglong2 v;
    asm volatile("ld.relaxed.gpu.global.v2.b64 {%0, %1}, [%2];" : "=l"(v.x), "=l"(v.y) : "l"(p) : "memory");
    return v;
}

__global__ void __launch_bounds__(NCT + 32, 1)
decode_kernel(const uint16_t* __restrict__ q, const int* __restrict__ qk, const int* __restrict__ qv,
              const uint16_t* __restrict__ ks, const uint16_t* __restrict__ kz,
              const uint16_t* __restrict__ vs, const uint16_t* __restrict__ vz,
              __nv_bfloat16* __restrict__ out) {
    extern __shared__ __align__(128) unsigned char smem_raw[];
    Smem& sm = *reinterpret_cast<Smem*>(smem_raw);
    const int tid = threadIdx.x, warp = tid >> 5, lane = tid & 31;
    const int G = gridDim.x, b = blockIdx.x;

    if (warp == CW) {
        uint64_t pol;
        asm volatile("createpolicy.fractional.L2::evict_first.b64 %0, 1.0;" : "=l"(pol));
        auto issue = [&](int t, int s) {
            sm.tile[s] = t;
            const uint32_t bk = smem_u32(&sm.fullK[s]), bv = smem_u32(&sm.fullV[s]);
            mbar_expect_tx(bk, TILE_BYTES + 2 * TT * 2);
            bulk_load(smem_u32(&sm.kv[s][0][0]), qk + (size_t)t * (TT * DH), TILE_BYTES, bk, pol);
            mbar_expect_tx(bv, TILE_BYTES);
            bulk_load(smem_u32(&sm.kv[s][1][0]), qv + (size_t)t * (TT * DH), TILE_BYTES, bv, pol);
            bulk_load(smem_u32(&sm.vs[s][0]), vs + (size_t)t * TT, TT * 2, bk, pol);
            bulk_load(smem_u32(&sm.vz[s][0]), vz + (size_t)t * TT, TT * 2, bk, pol);
        };
        unsigned nxt = 0;
        if (lane == 0) {
#pragma unroll
            for (int s = 0; s < NST; s++) {
                mbar_init(smem_u32(&sm.fullK[s]), 1);
                mbar_init(smem_u32(&sm.fullV[s]), 1);
                mbar_init(smem_u32(&sm.empty[s]), CW);
            }
            mbar_init(smem_u32(&sm.parbar), 1);
            asm volatile("fence.mbarrier_init.release.cluster;" ::: "memory");
            asm volatile("fence.proxy.async.shared::cta;" ::: "memory");
            issue(b, 0);
            {
                const uint32_t pb = smem_u32(&sm.parbar);
                mbar_expect_tx(pb, (HQ * DH + 2 * HKV * NGK * DH) * 2);
                bulk_load_nohint(smem_u32(sm.q), q, HQ * DH * 2, pb);
                bulk_load_nohint(smem_u32(sm.ks), ks, HKV * NGK * DH * 2, pb);
                bulk_load_nohint(smem_u32(sm.kz), kz, HKV * NGK * DH * 2, pb);
            }
#pragma unroll
            for (int s = 1; s < NST; s++) issue(b + s * G, s);
            nxt = atomicAdd(&g_ctr, 1u);
        }
        __syncwarp();
        __syncthreads();
        if (lane == 0) {
            int s = 0;
            uint32_t ph = 0;
            while (true) {
                const int t = (int)nxt + NST * G;
                if (t < NTILES) nxt = atomicAdd(&g_ctr, 1u);
                mbar_wait(smem_u32(&sm.empty[s]), ph);
                if (t >= NTILES) {
                    sm.tile[s] = -1;
                    mbar_arrive(smem_u32(&sm.fullK[s]));
                    break;
                }
                issue(t, s);
                if (++s == NST) { s = 0; ph ^= 1; }
            }
        }
        return;
    }

    if (tid == 0) {
        unsigned e;
        asm volatile("ld.relaxed.gpu.global.u32 %0, [%1];" : "=r"(e) : "l"(&g_epoch) : "memory");
        sm.epoch = e;
    }
    __syncthreads();
    const uint32_t epoch = sm.epoch;
    const uint32_t tag = epoch + 1;
    mbar_wait(smem_u32(&sm.parbar), 0);

    const int r = lane >> 3, c = lane & 7;
    const bool hi = (c & 4) != 0;
    const float NEG_INF = __int_as_float(0xff800000);
    const float QSCALE = 0.08838834764831845f * 1.4426950408889634f;

    float qs0[16], qs1[16], bias0 = 0.f, bias1 = 0.f;
    float acc0[4] = {0.f, 0.f, 0.f, 0.f}, acc1[4] = {0.f, 0.f, 0.f, 0.f};
    float m_own = NEG_INF, l_own = 0.f, z_own = 0.f;
    int cur_hg = -1;
    int cur_head = 0;

    auto flush = [&](int head) {
        float l = l_own, z = z_own;
        l += __shfl_xor_sync(0xffffffffu, l, 8);
        z += __shfl_xor_sync(0xffffffffu, z, 8);
        l += __shfl_xor_sync(0xffffffffu, l, 16);
        z += __shfl_xor_sync(0xffffffffu, z, 16);
        const float z0 = __shfl_sync(0xffffffffu, z, 0), z1 = __shfl_sync(0xffffffffu, z, 4);
        *reinterpret_cast<float4*>(&sm.wacc[warp][0][lane * 4]) =
            make_float4(acc0[0] - z0, acc0[1] - z0, acc0[2] - z0, acc0[3] - z0);
        *reinterpret_cast<float4*>(&sm.wacc[warp][1][lane * 4]) =
            make_float4(acc1[0] - z1, acc1[1] - z1, acc1[2] - z1, acc1[3] - z1);
        if (lane == 0 || lane == 4) {
            sm.wm[warp][lane >> 2] = m_own;
            sm.wl[warp][lane >> 2] = l;
        }
        cons_sync();
        const int h = tid >> 7, d = tid & 127;
        float M = NEG_INF;
#pragma unroll
        for (int w = 0; w < CW; w++) M = fmaxf(M, sm.wm[w][h]);
        float o = 0.f, L = 0.f, lse = NEG_INF;
        if (M != NEG_INF) {
#pragma unroll
            for (int w = 0; w < CW; w++) {
                const float e = ex2(sm.wm[w][h] - M);
                o += e * sm.wacc[w][h][d];
                L += e * sm.wl[w][h];
            }
            o = o / L;
            lse = M + log2f(L);
        }
        const int qh = head * REP + h;
        st_relaxed_u64(reinterpret_cast<unsigned long long*>(&g_part[qh][b][0]) + d, pack_tag(o, tag));
        if (d == 0) st_relaxed_u64(&g_lse[qh][b], pack_tag(lse, tag));
        cons_sync();
        m_own = NEG_INF; l_own = 0.f; z_own = 0.f;
#pragma unroll
        for (int i = 0; i < 4; i++) { acc0[i] = 0.f; acc1[i] = 0.f; }
    };

    int s = 0;
    uint32_t ph = 0;
    while (true) {
        mbar_wait(smem_u32(&sm.fullK[s]), ph);
        const int t = sm.tile[s];
        if (t < 0) break;
        const int hg = t / TILES_PER_GROUP;
        if (hg != cur_hg) {
            const int head = hg / NGK;
            while (cur_head < head) { flush(cur_head); cur_head++; }
            cur_hg = hg;
            bias0 = 0.f; bias1 = 0.f;
#pragma unroll
            for (int j = 0; j < 4; j++) {
                const int d0 = 4 * (c + 8 * j);
                const uint2 qa = *reinterpret_cast<const uint2*>(&sm.q[(head * REP) * DH + d0]);
                const uint2 qb = *reinterpret_cast<const uint2*>(&sm.q[(head * REP + 1) * DH + d0]);
                const uint2 sc = *reinterpret_cast<const uint2*>(&sm.ks[hg * DH + d0]);
                const uint2 zz = *reinterpret_cast<const uint2*>(&sm.kz[hg * DH + d0]);
                const uint32_t qaw[2] = {qa.x, qa.y}, qbw[2] = {qb.x, qb.y}, scw[2] = {sc.x, sc.y}, zzw[2] = {zz.x, zz.y};
#pragma unroll
                for (int i = 0; i < 4; i++) {
                    const int sh = (i & 1) * 16;
                    const float fs = bf2f((scw[i >> 1] >> sh) & 0xffffu) * QSCALE;
                    const float fz = bf2f((zzw[i >> 1] >> sh) & 0xffffu);
                    const float a = bf2f((qaw[i >> 1] >> sh) & 0xffffu) * fs;
                    const float bb = bf2f((qbw[i >> 1] >> sh) & 0xffffu) * fs;
                    qs0[j * 4 + i] = a;
                    qs1[j * 4 + i] = bb;
                    bias0 -= a * fz;
                    bias1 -= bb * fz;
                }
            }
        }
        const int4* kp = &sm.kv[s][0][(warp * 4 + r) * 32 + c];
        int4 kx[4];
#pragma unroll
        for (int j = 0; j < 4; j++) kx[j] = kp[8 * j];
        const float vsc = bf2f(sm.vs[s][warp * 4 + r]);
        const float vzr = bf2f(sm.vz[s][warp * 4 + r]);
        float s0a = bias0, s1a = bias1, s0b = 0.f, s1b = 0.f;
#pragma unroll
        for (int j = 0; j < 4; j++) {
            const float f0 = (float)kx[j].x, f1 = (float)kx[j].y, f2 = (float)kx[j].z, f3 = (float)kx[j].w;
            s0a = fmaf(qs0[j * 4 + 0], f0, s0a); s1a = fmaf(qs1[j * 4 + 0], f0, s1a);
            s0b = fmaf(qs0[j * 4 + 1], f1, s0b); s1b = fmaf(qs1[j * 4 + 1], f1, s1b);
            s0a = fmaf(qs0[j * 4 + 2], f2, s0a); s1a = fmaf(qs1[j * 4 + 2], f2, s1a);
            s0b = fmaf(qs0[j * 4 + 3], f3, s0b); s1b = fmaf(qs1[j * 4 + 3], f3, s1b);
        }
        const float s0 = s0a + s0b, s1 = s1a + s1b;
        float v = (hi ? s1 : s0) + __shfl_xor_sync(0xffffffffu, hi ? s0 : s1, 4);
        v += __shfl_xor_sync(0xffffffffu, v, 2);
        v += __shfl_xor_sync(0xffffffffu, v, 1);
        if (__any_sync(0xffffffffu, v > m_own)) {
            float tmax = fmaxf(v, __shfl_xor_sync(0xffffffffu, v, 8));
            tmax = fmaxf(tmax, __shfl_xor_sync(0xffffffffu, tmax, 16));
            const float mn = fmaxf(m_own, tmax);
            const float alpha = ex2(m_own - mn);
            l_own *= alpha;
            z_own *= alpha;
            const float a0 = __shfl_sync(0xffffffffu, alpha, 0), a1 = __shfl_sync(0xffffffffu, alpha, 4);
#pragma unroll
            for (int i = 0; i < 4; i++) { acc0[i] *= a0; acc1[i] *= a1; }
            m_own = mn;
        }
        const float p = ex2(v - m_own);
        l_own += p;
        const float w = p * vsc;
        z_own = fmaf(w, vzr, z_own);
        float w0[4], w1[4];
#pragma unroll
        for (int k = 0; k < 4; k++) {
            w0[k] = __shfl_sync(0xffffffffu, w, k * 8);
            w1[k] = __shfl_sync(0xffffffffu, w, k * 8 + 4);
        }
        mbar_wait(smem_u32(&sm.fullV[s]), ph);
        const int4* vp = &sm.kv[s][1][(warp * 4) * 32 + lane];
        int4 vx[4];
#pragma unroll
        for (int k = 0; k < 4; k++) vx[k] = vp[32 * k];
#pragma unroll
        for (int k = 0; k < 4; k++) {
            const float f0 = (float)vx[k].x, f1 = (float)vx[k].y, f2 = (float)vx[k].z, f3 = (float)vx[k].w;
            acc0[0] = fmaf(w0[k], f0, acc0[0]); acc1[0] = fmaf(w1[k], f0, acc1[0]);
            acc0[1] = fmaf(w0[k], f1, acc0[1]); acc1[1] = fmaf(w1[k], f1, acc1[1]);
            acc0[2] = fmaf(w0[k], f2, acc0[2]); acc1[2] = fmaf(w1[k], f2, acc1[2]);
            acc0[3] = fmaf(w0[k], f3, acc0[3]); acc1[3] = fmaf(w1[k], f3, acc1[3]);
        }
        __syncwarp();
        if (lane == 0) mbar_arrive(smem_u32(&sm.empty[s]));
        if (++s == NST) { s = 0; ph ^= 1; }
    }
    while (cur_head < HKV) { flush(cur_head); cur_head++; }

    constexpr int NI = MAXG / 16;
    for (int cb = b; cb < NCOLB; cb += G) {
        const int qh = cb >> 2, col = (cb & 3) * 16 + (tid & 15), sg = tid >> 4;
        ulonglong2 pv[NI];
        unsigned long long pl[NI];
        for (uint32_t it = 0;; ++it) {
            bool ok = true;
#pragma unroll
            for (int i = 0; i < NI; i++) {
                const int slot = sg + 16 * i;
                if (slot < G) {
                    pv[i] = ld_relaxed_v2u64(&g_part[qh][slot][col]);
                    pl[i] = ld_relaxed_u64(&g_lse[qh][slot]);
                }
            }
#pragma unroll
            for (int i = 0; i < NI; i++) {
                const int slot = sg + 16 * i;
                if (slot < G)
                    ok = ok && (uint32_t)(pv[i].x >> 32) == tag && (uint32_t)(pv[i].y >> 32) == tag &&
                         (uint32_t)(pl[i] >> 32) == tag;
            }
            if (ok) break;
            if (it > (1u << 22)) __trap();
        }
        float m = NEG_INF;
#pragma unroll
        for (int i = 0; i < NI; i++)
            if (sg + 16 * i < G) m = fmaxf(m, __uint_as_float((uint32_t)pl[i]));
        m = fmaxf(m, __shfl_xor_sync(0xffffffffu, m, 16));
        float o0 = 0.f, o1 = 0.f, ws = 0.f;
        if (m != NEG_INF) {
#pragma unroll
            for (int i = 0; i < NI; i++)
                if (sg + 16 * i < G) {
                    const float e = ex2(__uint_as_float((uint32_t)pl[i]) - m);
                    ws += e;
                    o0 = fmaf(e, __uint_as_float((uint32_t)pv[i].x), o0);
                    o1 = fmaf(e, __uint_as_float((uint32_t)pv[i].y), o1);
                }
        }
        ws += __shfl_xor_sync(0xffffffffu, ws, 16);
        o0 += __shfl_xor_sync(0xffffffffu, o0, 16);
        o1 += __shfl_xor_sync(0xffffffffu, o1, 16);
        if (lane < 16) sm.fin[warp][lane] = make_float4(m, ws, o0, o1);
        cons_sync();
        if (tid < 16) {
            float M = NEG_INF;
#pragma unroll
            for (int w = 0; w < CW; w++) M = fmaxf(M, sm.fin[w][tid].x);
            float W = 0.f, a0 = 0.f, a1 = 0.f;
#pragma unroll
            for (int w = 0; w < CW; w++) {
                const float4 f = sm.fin[w][tid];
                const float e = (f.x == NEG_INF) ? 0.f : ex2(f.x - M);
                W = fmaf(e, f.y, W);
                a0 = fmaf(e, f.z, a0);
                a1 = fmaf(e, f.w, a1);
            }
            const float inv = 1.f / W;
            *reinterpret_cast<__nv_bfloat162*>(out + qh * DH + col * 2) = __floats2bfloat162_rn(a0 * inv, a1 * inv);
        }
        if (cb == NCOLB - 1 && tid == 0) {
            g_ctr = 0;
            g_epoch = epoch + 1;
        }
        cons_sync();
    }
}

}

extern "C" void kernel_launch(void* const* d_in, const int* in_sizes, int n_in, void* d_out, int out_size) {
    (void)in_sizes; (void)n_in; (void)out_size;
    static int grid = 0;
    if (grid == 0) {
        int dev = 0, sms = 0;
        cudaGetDevice(&dev);
        cudaDeviceGetAttribute(&sms, cudaDevAttrMultiProcessorCount, dev);
        cudaFuncSetAttribute(kvq::decode_kernel, cudaFuncAttributeMaxDynamicSharedMemorySize, (int)sizeof(kvq::Smem));
        grid = sms < kvq::MAXG ? sms : kvq::MAXG;
    }
    kvq::decode_kernel<<<grid, kvq::NCT + 32, sizeof(kvq::Smem)>>>(
        (const uint16_t*)d_in[0], (const int*)d_in[1], (const int*)d_in[2], (const uint16_t*)d_in[3],
        (const uint16_t*)d_in[4], (const uint16_t*)d_in[5], (const uint16_t*)d_in[6], (__nv_bfloat16*)d_out);
}
```

```cpp
#include <cuda_runtime.h>
#include <cuda.h>
#include <cuda_bf16.h>
#include <stdint.h>

namespace kvq {

constexpr int HKV = 16, SKV = 65536, DH = 128, REP = 2, NGK = 2;
constexpr int HQ = HKV * REP;
constexpr int GROUP = SKV / NGK;
constexpr int TT = 32;
constexpr int TILE_BYTES = TT * DH * 4;
constexpr int NST = 4;
constexpr int CW = 8;
constexpr int NCT = CW * 32;
constexpr int NTILES = HKV * SKV / TT;
constexpr int TILES_PER_GROUP = GROUP / TT;
constexpr int TILES_PER_HEAD = SKV / TT;
constexpr int XT = 32;
constexpr int XT0 = 512;
constexpr int NSL = 8;
constexpr int SL_ROWS = TILE_BYTES / (DH / NSL * 4);
constexpr int NP = XT * TT / SL_ROWS;
constexpr int NTASK = HKV * NSL;
constexpr int MAXG = 144;
constexpr int NCOL = DH / 2;
constexpr int CPT = REP * NCOL / NSL;
constexpr int SPP = NCT / CPT;
constexpr int NI = (MAXG + SPP - 1) / SPP;
constexpr int PF_TILES = 128, PF_DIST = 1024;
static_assert(NST >= 4, "the producer may look back three items");
static_assert(2 * MAXG <= XT0 && XT0 + XT <= TILES_PER_GROUP && SL_ROWS == NCT && CPT == 16, "layout assumptions");

__device__ unsigned int g_ctr;
__device__ unsigned int g_epoch;
__device__ __align__(128) uint4 g_part[MAXG][HQ][NCOL];
__device__ __align__(128) uint4 g_tail[HKV][XT * TT];

struct __align__(128) Smem {
    int4 kv[NST][2][TT * DH / 4];
    uint16_t vs[NST][TT];
    uint16_t vz[NST][TT];
    uint16_t q[HQ * DH];
    uint16_t ks[HKV * NGK * DH];
    uint16_t kz[HKV * NGK * DH];
    float wacc[2][CW][REP][DH];
    float2 wml[2][REP][CW];
    float2 wt[XT * TT];
    float4 fin[CW][CPT];
    float4 mres[CPT];
    float2 fin2[CW][CPT];
    float2 wmax[CW];
    float2 mt;
    unsigned long long fullK[NST], fullV[NST], meta[NST], empty[NST], parbar;
    int next[NST];
};

__device__ __forceinline__ uint32_t smem_u32(const void* p) { return (uint32_t)__cvta_generic_to_shared(p); }
__device__ __forceinline__ void mbar_init(uint32_t bar, int cnt) {
    asm volatile("mbarrier.init.shared::cta.b64 [%0], %1;" ::"r"(bar), "r"(cnt) : "memory");
}
__device__ __forceinline__ void mbar_expect_tx(uint32_t bar, uint32_t bytes) {
    asm volatile("mbarrier.arrive.expect_tx.shared::cta.b64 _, [%0], %1;" ::"r"(bar), "r"(bytes) : "memory");
}
__device__ __forceinline__ void mbar_arrive(uint32_t bar) {
    asm volatile("mbarrier.arrive.shared::cta.b64 _, [%0];" ::"r"(bar) : "memory");
}
__device__ __forceinline__ bool mbar_try(uint32_t bar, uint32_t parity) {
    uint32_t ok;
    asm volatile(
        "{\n.reg .pred p;\n"
        "mbarrier.try_wait.parity.shared::cta.b64 p, [%1], %2;\n"
        "selp.u32 %0, 1, 0, p;\n}"
        : "=r"(ok) : "r"(bar), "r"(parity) : "memory");
    return ok != 0;
}
__device__ __forceinline__ void mbar_wait(uint32_t bar, uint32_t parity) {
    uint32_t it = 0;
#pragma unroll 1
    while (!mbar_try(bar, parity)) {
        if (++it > (1u << 24)) __trap();
    }
}
__device__ __forceinline__ void bulk_load(uint32_t dst, const void* src, uint32_t bytes, uint32_t bar, uint64_t pol) {
    asm volatile(
        "cp.async.bulk.shared::cluster.global.mbarrier::complete_tx::bytes.L2::cache_hint [%0], [%1], %2, [%3], %4;"
        ::"r"(dst), "l"(src), "r"(bytes), "r"(bar), "l"(pol) : "memory");
}
__device__ __forceinline__ void bulk_load_nohint(uint32_t dst, const void* src, uint32_t bytes, uint32_t bar) {
    asm volatile(
        "cp.async.bulk.shared::cluster.global.mbarrier::complete_tx::bytes [%0], [%1], %2, [%3];"
        ::"r"(dst), "l"(src), "r"(bytes), "r"(bar) : "memory");
}
__device__ __forceinline__ void tensor_load_2d(uint32_t dst, const CUtensorMap* map, int c0, int c1, uint32_t bar,
                                               uint64_t pol) {
    asm volatile(
        "cp.async.bulk.tensor.2d.shared::cluster.global.mbarrier::complete_tx::bytes.L2::cache_hint "
        "[%0], [%1, {%3, %4}], [%2], %5;"
        ::"r"(dst), "l"(map), "r"(bar), "r"(c0), "r"(c1), "l"(pol) : "memory");
}
__device__ __forceinline__ void bulk_prefetch_l2(const void* src, uint32_t bytes) {
    asm volatile("cp.async.bulk.prefetch.L2.global [%0], %1;" ::"l"(src), "r"(bytes) : "memory");
}
__device__ __forceinline__ float ex2(float x) {
    float y;
    asm("ex2.approx.ftz.f32 %0, %1;" : "=f"(y) : "f"(x));
    return y;
}
__device__ __forceinline__ float lg2(float x) {
    float y;
    asm("lg2.approx.ftz.f32 %0, %1;" : "=f"(y) : "f"(x));
    return y;
}
__device__ __forceinline__ float bf2f(uint32_t lo16) { return __uint_as_float(lo16 << 16); }
__device__ __forceinline__ void cons_sync() { asm volatile("bar.sync 1, %0;" ::"n"(NCT) : "memory"); }
__device__ __forceinline__ bool cons_sync_or(bool c) {
    uint32_t r;
    asm volatile("{\n.reg .pred p, q;\nsetp.ne.u32 q, %1, 0;\nbar.red.or.pred p, 2, %2, q;\nselp.u32 %0, 1, 0, p;\n}"
                 : "=r"(r) : "r"((uint32_t)c), "n"(NCT) : "memory");
    return r != 0;
}
__device__ __forceinline__ void st_relaxed_b128(uint4* p, uint32_t x, uint32_t y, uint32_t z, uint32_t w) {
    asm volatile("{\n.reg .b128 t;\nmov.b128 t, {%1, %2, %3, %4};\nst.relaxed.gpu.global.b128 [%0], t;\n}"
                 ::"l"(p), "r"(x), "r"(y), "r"(z), "r"(w) : "memory");
}
__device__ __forceinline__ uint4 ld_relaxed_b128(const uint4* p) {
    uint4 v;
    asm volatile("{\n.reg .b128 t;\nld.relaxed.gpu.global.b128 t, [%4];\nmov.b128 {%0, %1, %2, %3}, t;\n}"
                 : "=r"(v.x), "=r"(v.y), "=r"(v.z), "=r"(v.w) : "l"(p) : "memory");
    return v;
}
__device__ __forceinline__ unsigned atom_inc(unsigned* p, unsigned lim) {
    unsigned r;
    asm volatile("atom.relaxed.gpu.global.inc.u32 %0, [%1], %2;" : "=r"(r) : "l"(p), "r"(lim) : "memory");
    return r;
}
__device__ __forceinline__ bool deferred(int t) {
    return (unsigned)(t % TILES_PER_HEAD - XT0) < (unsigned)XT && t < NTILES - TILES_PER_HEAD;
}

__global__ void __launch_bounds__(NCT + 32, 1)
decode_kernel(const uint16_t* __restrict__ q, const int* __restrict__ qk, const int* __restrict__ qv,
              const uint16_t* __restrict__ ks, const uint16_t* __restrict__ kz,
              const uint16_t* __restrict__ vs, const uint16_t* __restrict__ vz,
              __nv_bfloat16* __restrict__ out, const __grid_constant__ CUtensorMap vmap) {
    extern __shared__ __align__(128) unsigned char smem_raw[];
    Smem& sm = *reinterpret_cast<Smem*>(smem_raw);
    const int tid = threadIdx.x, warp = tid >> 5, lane = tid & 31;
    const int G = gridDim.x, b = blockIdx.x;

    uint64_t pol;
    asm volatile("createpolicy.fractional.L2::evict_first.b64 %0, 1.0;" : "=l"(pol));
    auto issueK = [&](int t, int s) {
        const uint32_t bk = smem_u32(&sm.fullK[s]);
        mbar_expect_tx(bk, TILE_BYTES + 2 * TT * 2);
        bulk_load(smem_u32(&sm.kv[s][0][0]), qk + (size_t)t * (TT * DH), TILE_BYTES, bk, pol);
        bulk_load(smem_u32(&sm.vs[s][0]), vs + (size_t)t * TT, TT * 2, bk, pol);
        bulk_load(smem_u32(&sm.vz[s][0]), vz + (size_t)t * TT, TT * 2, bk, pol);
        if ((t & (PF_TILES - 1)) == 0 && t + PF_DIST < NTILES) {
            bulk_prefetch_l2(vs + (size_t)(t + PF_DIST) * TT, PF_TILES * TT * 2);
            bulk_prefetch_l2(vz + (size_t)(t + PF_DIST) * TT, PF_TILES * TT * 2);
        }
    };
    auto issueV = [&](int t, int s) {
        const uint32_t bv = smem_u32(&sm.fullV[s]);
        mbar_expect_tx(bv, TILE_BYTES);
        bulk_load(smem_u32(&sm.kv[s][1][0]), qv + (size_t)t * (TT * DH), TILE_BYTES, bv, pol);
    };
    if (tid == NCT) {
#pragma unroll
        for (int s = 0; s < NST; s++) {
            mbar_init(smem_u32(&sm.fullK[s]), 1);
            mbar_init(smem_u32(&sm.fullV[s]), 1);
            mbar_init(smem_u32(&sm.meta[s]), 1);
            mbar_init(smem_u32(&sm.empty[s]), CW);
        }
        mbar_init(smem_u32(&sm.parbar), 1);
        asm volatile("fence.mbarrier_init.release.cluster;" ::: "memory");
        asm volatile("fence.proxy.async.shared::cta;" ::: "memory");
        issueK(b, 0);
        issueV(b, 0);
    }
    __syncthreads();

    if (warp == CW) {
        if (lane == 0) {
            const unsigned lim = (unsigned)(NTILES - 2 * G + G - 1);
            sm.next[0] = b + G;
            mbar_arrive(smem_u32(&sm.meta[0]));
            uint32_t w0 = smem_u32(&sm.empty[NST - 1]) | 1u, w1 = smem_u32(&sm.fullK[0]), w2 = smem_u32(&sm.fullV[0]);
            uint32_t plast = clock(), pacc = 0;
            auto pace = [&](uint32_t wnew) {
                mbar_wait(w0 & ~1u, w0 & 1u);
                w0 = w1; w1 = w2; w2 = wnew;
                const uint32_t pbar = pacc >> 4;
                const uint32_t gap = pbar - ((pbar * 20u) >> 8);
                uint32_t now = clock();
                while (now - plast < gap) now = clock();
                pacc += min(now - plast, pbar + (pbar >> 1) + 512u) - pbar;
                plast = now;
            };
            int t = b + G, s = 1;
            uint32_t ph = 0;
            bool first = true;
            while (true) {
                mbar_wait(smem_u32(&sm.empty[s]), ph ^ 1);
                pace(smem_u32(&sm.fullK[s]) | ph);
                issueK(t, s);
                const unsigned nxt = atom_inc(&g_ctr, lim);
                if (first) {
                    first = false;
                    const uint32_t pb = smem_u32(&sm.parbar);
                    mbar_expect_tx(pb, (HQ * DH + 2 * HKV * NGK * DH) * 2);
                    bulk_load_nohint(smem_u32(sm.q), q, HQ * DH * 2, pb);
                    bulk_load_nohint(smem_u32(sm.ks), ks, HKV * NGK * DH * 2, pb);
                    bulk_load_nohint(smem_u32(sm.kz), kz, HKV * NGK * DH * 2, pb);
                }
                if (!deferred(t)) {
                    pace(smem_u32(&sm.fullV[s]) | ph);
                    issueV(t, s);
                } else {
                    mbar_arrive(smem_u32(&sm.fullV[s]));
                    mbar_wait(smem_u32(&sm.fullV[s]), ph);
                }
                if (t >= NTILES - 4 * G) asm volatile("prefetch.tensormap [%0];" ::"l"(&vmap) : "memory");
                t = (int)nxt + 2 * G;
                sm.next[s] = t;
                mbar_arrive(smem_u32(&sm.meta[s]));
                if (++s == NST) { s = 0; ph ^= 1; }
                if (t >= NTILES) break;
            }
            for (int task = b; task < NTASK - NSL; task += G) {
                const int row0 = (task / NSL) * SKV + XT0 * TT;
                for (int j = 0; j < NP; j++) {
                    mbar_wait(smem_u32(&sm.empty[s]), ph ^ 1);
                    const uint32_t bv = smem_u32(&sm.fullV[s]);
                    pace(bv | ph);
                    mbar_expect_tx(bv, TILE_BYTES);
                    tensor_load_2d(smem_u32(&sm.kv[s][1][0]), &vmap, (task % NSL) * (DH / NSL), row0 + j * SL_ROWS, bv, pol);
                    if (++s == NST) { s = 0; ph ^= 1; }
                }
            }
        }
        return;
    }

    uint32_t epoch;
    asm volatile("ld.relaxed.gpu.global.u32 %0, [%1];" : "=r"(epoch) : "l"(&g_epoch) : "memory");
    mbar_wait(smem_u32(&sm.parbar), 0);
    const uint32_t tag = epoch + 1;

    const int r = lane >> 3, c = lane & 7;
    const bool hi = (c & 4) != 0;
    const float NEG_INF = __int_as_float(0xff800000);
    const float QSCALE = 0.08838834764831845f * 1.4426950408889634f;

    float qs0[16], qs1[16], bias0 = 0.f, bias1 = 0.f;
    float acc0[4] = {0.f, 0.f, 0.f, 0.f}, acc1[4] = {0.f, 0.f, 0.f, 0.f};
    float m_own = NEG_INF, l_own = 0.f, z_own = 0.f;
    float lse0 = NEG_INF, lse1 = NEG_INF;
    bool lse_last = false;
    int cur_hg = -1;
    int wbuf = 0, abuf = 0;
    int t = b;
    int s = 0;
    uint32_t ph = 0;
    int task = b, prep = 0;

    while (true) {
        const int hg = t < NTILES ? t / TILES_PER_GROUP : HKV * NGK + 1;
        if (hg != cur_hg) {
            const int fh = task / NSL, sl = task % NSL;
            const int ci = tid & (CPT - 1), cq = ci >> 3;
            __nv_bfloat162* dst = reinterpret_cast<__nv_bfloat162*>(out + (fh * REP + cq) * DH + sl * (DH / NSL)) + (ci & 7);
            if (task < NTASK - NSL && prep == 0 && hg >= fh * NGK + 1) {
                prep = 1;
                uint4 e[NP];
                uint32_t it = 0;
                bool ok;
#pragma unroll 1
                do {
                    ok = true;
#pragma unroll
                    for (int j = 0; j < NP; j++) e[j] = ld_relaxed_b128(&g_tail[fh][j * SL_ROWS + tid]);
#pragma unroll
                    for (int j = 0; j < NP; j++) ok = ok && e[j].w == tag;
                    if (++it > (1u << 22)) __trap();
                } while (__any_sync(0xffffffffu, !ok));
                float mt0 = NEG_INF, mt1 = NEG_INF;
#pragma unroll
                for (int j = 0; j < NP; j++) {
                    mt0 = fmaxf(mt0, __uint_as_float(e[j].x));
                    mt1 = fmaxf(mt1, __uint_as_float(e[j].y));
                }
#pragma unroll
                for (int o = 16; o > 0; o >>= 1) {
                    mt0 = fmaxf(mt0, __shfl_xor_sync(0xffffffffu, mt0, o));
                    mt1 = fmaxf(mt1, __shfl_xor_sync(0xffffffffu, mt1, o));
                }
                if (lane == 0) sm.wmax[warp] = make_float2(mt0, mt1);
                cons_sync();
#pragma unroll
                for (int w = 0; w < CW; w++) { mt0 = fmaxf(mt0, sm.wmax[w].x); mt1 = fmaxf(mt1, sm.wmax[w].y); }
#pragma unroll
                for (int j = 0; j < NP; j++)
                    sm.wt[j * SL_ROWS + tid] = make_float2(ex2(__uint_as_float(e[j].x) - mt0) * __uint_as_float(e[j].z),
                                                           ex2(__uint_as_float(e[j].y) - mt1) * __uint_as_float(e[j].z));
                if (tid == 0) sm.mt = make_float2(mt0, mt1);
                cons_sync();
            }
            if (task < NTASK && prep < 2 && hg >= fh * NGK + 3) {
                prep = 2;
                const int slot0 = tid / CPT;
                const uint4* src = &g_part[slot0][fh * REP + cq][sl * (CPT / 2) + (ci & 7)];
                uint4 v[NI];
                uint32_t pend = 0;
#pragma unroll
                for (int i = 0; i < NI; i++) {
                    v[i] = make_uint4(0u, 0u, 0xff800000u, 0u);
                    if (slot0 + i * SPP < G) pend |= 1u << i;
                }
                const float mt = fh < HKV - 1 ? (cq ? sm.mt.y : sm.mt.x) : (lse_last ? (cq ? lse1 : lse0) : NEG_INF);
                float R = mt;
                uint32_t it = 0;
#pragma unroll 1
                do {
#pragma unroll
                    for (int i = 0; i < NI; i++)
                        if (pend & (1u << i)) v[i] = ld_relaxed_b128(src + (size_t)i * SPP * HQ * NCOL);
#pragma unroll
                    for (int i = 0; i < NI; i++)
                        if (v[i].w == tag) pend &= ~(1u << i);
                    if (++it > (1u << 22)) __trap();
                } while (__any_sync(0xffffffffu, pend != 0));
#pragma unroll 1
                for (int pass = 0; pass < 2; pass++) {
                    float ws = 0.f, o0 = 0.f, o1 = 0.f;
                    bool bad = false;
#pragma unroll
                    for (int i = 0; i < NI; i++) {
                        const float d = __uint_as_float(v[i].z) - R;
                        bad = bad || !(d <= 32.f);
                        const float e = ex2(d);
                        ws += e;
                        o0 = fmaf(e, __uint_as_float(v[i].x), o0);
                        o1 = fmaf(e, __uint_as_float(v[i].y), o1);
                    }
                    ws += __shfl_xor_sync(0xffffffffu, ws, 16);
                    o0 += __shfl_xor_sync(0xffffffffu, o0, 16);
                    o1 += __shfl_xor_sync(0xffffffffu, o1, 16);
                    if (lane < CPT) sm.fin[warp][lane] = make_float4(ws, o0, o1, 0.f);
                    if (!cons_sync_or(bad)) break;
                    float m = NEG_INF;
#pragma unroll
                    for (int i = 0; i < NI; i++) m = fmaxf(m, __uint_as_float(v[i].z));
                    m = fmaxf(m, __shfl_xor_sync(0xffffffffu, m, 16));
                    const float mo = __shfl_xor_sync(0xffffffffu, m, 8);
                    if (lane == 0) sm.wmax[warp] = make_float2(m, mo);
                    cons_sync();
#pragma unroll
                    for (int w = 0; w < CW; w++) m = fmaxf(m, cq ? sm.wmax[w].y : sm.wmax[w].x);
                    R = m;
                    cons_sync();
                }
                if (tid < CPT) {
                    float4 f[CW];
#pragma unroll
                    for (int w = 0; w < CW; w++) f[w] = sm.fin[w][tid];
#pragma unroll
                    for (int o = CW / 2; o > 0; o >>= 1)
#pragma unroll
                        for (int w = 0; w < o; w++) { f[w].x += f[w + o].x; f[w].y += f[w + o].y; f[w].z += f[w + o].z; }
                    const float inv = __fdividef(1.f, f[0].x);
                    if (fh == HKV - 1) *dst = __floats2bfloat162_rn(f[0].y * inv, f[0].z * inv);
                    else sm.mres[tid] = make_float4(f[0].y * inv, f[0].z * inv, ex2(mt - R) * inv, 0.f);
                    if (task == NTASK - 1 && tid == 0) g_epoch = tag;
                }
            }
            if (t >= NTILES) {
                if (task < NTASK - NSL) {
#pragma unroll 1
                    for (int j = 0; j < NP; j++) {
                        float2 wk[4];
#pragma unroll
                        for (int k = 0; k < 4; k++) wk[k] = sm.wt[j * SL_ROWS + warp * 32 + k * 8 + (lane >> 2)];
                        mbar_wait(smem_u32(&sm.fullV[s]), ph);
                        const int4* vp = &sm.kv[s][1][warp * 128 + lane];
                        int4 vx[4];
#pragma unroll
                        for (int k = 0; k < 4; k++) vx[k] = vp[32 * k];
#pragma unroll
                        for (int k = 0; k < 4; k++) {
                            const float f0 = (float)vx[k].x, f1 = (float)vx[k].y, f2 = (float)vx[k].z, f3 = (float)vx[k].w;
                            acc0[0] = fmaf(wk[k].x, f0, acc0[0]); acc1[0] = fmaf(wk[k].y, f0, acc1[0]);
                            acc0[1] = fmaf(wk[k].x, f1, acc0[1]); acc1[1] = fmaf(wk[k].y, f1, acc1[1]);
                            acc0[2] = fmaf(wk[k].x, f2, acc0[2]); acc1[2] = fmaf(wk[k].y, f2, acc1[2]);
                            acc0[3] = fmaf(wk[k].x, f3, acc0[3]); acc1[3] = fmaf(wk[k].y, f3, acc1[3]);
                        }
                        __syncwarp();
                        if (lane == 0) mbar_arrive(smem_u32(&sm.empty[s]));
                        if (++s == NST) { s = 0; ph ^= 1; }
                    }
                    const bool b4 = (lane & 16) != 0, b3 = (lane & 8) != 0;
                    float x[4];
#pragma unroll
                    for (int i = 0; i < 4; i++)
                        x[i] = (b4 ? acc1[i] : acc0[i]) + __shfl_xor_sync(0xffffffffu, b4 ? acc0[i] : acc1[i], 16);
                    float y0 = (b3 ? x[2] : x[0]) + __shfl_xor_sync(0xffffffffu, b3 ? x[0] : x[2], 8);
                    float y1 = (b3 ? x[3] : x[1]) + __shfl_xor_sync(0xffffffffu, b3 ? x[1] : x[3], 8);
                    y0 += __shfl_xor_sync(0xffffffffu, y0, 4);
                    y1 += __shfl_xor_sync(0xffffffffu, y1, 4);
                    if ((lane & 4) == 0)
                        sm.fin2[warp][(b4 ? 8 : 0) + (lane & 3) * 2 + (b3 ? 1 : 0)] = make_float2(y0, y1);
                    cons_sync();
                    if (tid < CPT) {
                        float2 g[CW];
#pragma unroll
                        for (int w = 0; w < CW; w++) g[w] = sm.fin2[w][tid];
                        const float4 mr = sm.mres[tid];
#pragma unroll
                        for (int o = CW / 2; o > 0; o >>= 1)
#pragma unroll
                            for (int w = 0; w < o; w++) { g[w].x += g[w + o].x; g[w].y += g[w + o].y; }
                        *dst = __floats2bfloat162_rn(fmaf(g[0].x, mr.z, mr.x), fmaf(g[0].y, mr.z, mr.y));
                    }
                }
                task += G;
                if (task >= NTASK) break;
                prep = 0;
#pragma unroll
                for (int i = 0; i < 4; i++) { acc0[i] = 0.f; acc1[i] = 0.f; }
                cons_sync();
                continue;
            }
            cur_hg = hg;
            const int qrow = (hg / NGK) * REP;
            bias0 = 0.f; bias1 = 0.f;
#pragma unroll
            for (int j = 0; j < 4; j++) {
                const int d0 = 4 * (c + 8 * j);
                const uint2 qa = *reinterpret_cast<const uint2*>(&sm.q[qrow * DH + d0]);
                const uint2 qb = *reinterpret_cast<const uint2*>(&sm.q[(qrow + 1) * DH + d0]);
                const uint2 sc = *reinterpret_cast<const uint2*>(&sm.ks[hg * DH + d0]);
                const uint2 zz = *reinterpret_cast<const uint2*>(&sm.kz[hg * DH + d0]);
                const uint32_t qaw[2] = {qa.x, qa.y}, qbw[2] = {qb.x, qb.y}, scw[2] = {sc.x, sc.y}, zzw[2] = {zz.x, zz.y};
#pragma unroll
                for (int i = 0; i < 4; i++) {
                    const int sh = (i & 1) * 16;
                    const float fs = bf2f((scw[i >> 1] >> sh) & 0xffffu) * QSCALE;
                    const float fz = bf2f((zzw[i >> 1] >> sh) & 0xffffu);
                    const float a = bf2f((qaw[i >> 1] >> sh) & 0xffffu) * fs;
                    const float bb = bf2f((qbw[i >> 1] >> sh) & 0xffffu) * fs;
                    qs0[j * 4 + i] = a;
                    qs1[j * 4 + i] = bb;
                    bias0 -= a * fz;
                    bias1 -= bb * fz;
                }
            }
        }

        mbar_wait(smem_u32(&sm.meta[s]), ph);
        const int tn = sm.next[s];
        const int head = t / TILES_PER_HEAD;
        const int nhead = min(tn / TILES_PER_HEAD, HKV);

        mbar_wait(smem_u32(&sm.fullK[s]), ph);
        const int4* kp = &sm.kv[s][0][(warp * 4 + r) * 32 + c];
        int4 kx[4];
#pragma unroll
        for (int j = 0; j < 4; j++) kx[j] = kp[8 * j];
        const float vsc = bf2f(sm.vs[s][warp * 4 + r]);
        const float vzr = bf2f(sm.vz[s][warp * 4 + r]);
        float s0a = bias0, s1a = bias1, s0b = 0.f, s1b = 0.f;
#pragma unroll
        for (int j = 0; j < 4; j++) {
            const float f0 = (float)kx[j].x, f1 = (float)kx[j].y, f2 = (float)kx[j].z, f3 = (float)kx[j].w;
            s0a = fmaf(qs0[j * 4 + 0], f0, s0a); s1a = fmaf(qs1[j * 4 + 0], f0, s1a);
            s0b = fmaf(qs0[j * 4 + 1], f1, s0b); s1b = fmaf(qs1[j * 4 + 1], f1, s1b);
            s0a = fmaf(qs0[j * 4 + 2], f2, s0a); s1a = fmaf(qs1[j * 4 + 2], f2, s1a);
            s0b = fmaf(qs0[j * 4 + 3], f3, s0b); s1b = fmaf(qs1[j * 4 + 3], f3, s1b);
        }
        const float s0 = s0a + s0b, s1 = s1a + s1b;
        float v = (hi ? s1 : s0) + __shfl_xor_sync(0xffffffffu, hi ? s0 : s1, 4);
        v += __shfl_xor_sync(0xffffffffu, v, 2);
        v += __shfl_xor_sync(0xffffffffu, v, 1);
        if (__any_sync(0xffffffffu, v > m_own)) {
            float tmax = fmaxf(v, __shfl_xor_sync(0xffffffffu, v, 8));
            tmax = fmaxf(tmax, __shfl_xor_sync(0xffffffffu, tmax, 16));
            const float mn = fmaxf(m_own, tmax);
            const float alpha = ex2(m_own - mn);
            l_own *= alpha;
            z_own *= alpha;
            const float a0 = __shfl_sync(0xffffffffu, alpha, 0), a1 = __shfl_sync(0xffffffffu, alpha, 4);
#pragma unroll
            for (int i = 0; i < 4; i++) { acc0[i] *= a0; acc1[i] *= a1; }
            m_own = mn;
        }
        const float p = ex2(v - m_own);
        l_own += p;
        float w = p * vsc;
        z_own = fmaf(w, vzr, z_own);
        if (deferred(t)) {
            const float vo = __shfl_xor_sync(0xffffffffu, v, 4);
            if (c == 0)
                st_relaxed_b128(&g_tail[head][(t % TILES_PER_HEAD - XT0) * TT + warp * 4 + r], __float_as_uint(v),
                                __float_as_uint(vo), __float_as_uint(vsc), tag);
        }

        if (nhead != head) {
            float l = l_own, z = z_own;
            l += __shfl_xor_sync(0xffffffffu, l, 8);
            z += __shfl_xor_sync(0xffffffffu, z, 8);
            l += __shfl_xor_sync(0xffffffffu, l, 16);
            z += __shfl_xor_sync(0xffffffffu, z, 16);
            if (lane == 0 || lane == 4) sm.wml[wbuf][lane >> 2][warp] = make_float2(m_own, l);
            cons_sync();
            float4 ml[CW / 2];
#pragma unroll
            for (int i = 0; i < CW / 2; i++)
                ml[i] = *reinterpret_cast<const float4*>(&sm.wml[wbuf][hi ? 1 : 0][2 * i]);
            wbuf ^= 1;
            float M = NEG_INF;
#pragma unroll
            for (int i = 0; i < CW / 2; i++) M = fmaxf(M, fmaxf(ml[i].x, ml[i].z));
            float L = 0.f;
#pragma unroll
            for (int i = 0; i < CW / 2; i++) {
                L = fmaf(ex2(ml[i].x - M), ml[i].y, L);
                L = fmaf(ex2(ml[i].z - M), ml[i].w, L);
            }
            const float f = __fdividef(ex2(m_own - M), L);
            const float lse = M + lg2(L);
            w *= f;
            z *= f;
            const float f0 = __shfl_sync(0xffffffffu, f, 0), f1 = __shfl_sync(0xffffffffu, f, 4);
            const float z0 = __shfl_sync(0xffffffffu, z, 0), z1 = __shfl_sync(0xffffffffu, z, 4);
            lse0 = __shfl_sync(0xffffffffu, lse, 0);
            lse1 = __shfl_sync(0xffffffffu, lse, 4);
            lse_last = head == HKV - 1;
#pragma unroll
            for (int i = 0; i < 4; i++) { acc0[i] = fmaf(acc0[i], f0, -z0); acc1[i] = fmaf(acc1[i], f1, -z1); }
            m_own = NEG_INF; l_own = 0.f; z_own = 0.f;
        }
        if (!deferred(t)) {
            float w0[4], w1[4];
#pragma unroll
            for (int k = 0; k < 4; k++) {
                w0[k] = __shfl_sync(0xffffffffu, w, k * 8);
                w1[k] = __shfl_sync(0xffffffffu, w, k * 8 + 4);
            }
            mbar_wait(smem_u32(&sm.fullV[s]), ph);
            const int4* vp = &sm.kv[s][1][(warp * 4) * 32 + lane];
            int4 vx[4];
#pragma unroll
            for (int k = 0; k < 4; k++) vx[k] = vp[32 * k];
#pragma unroll
            for (int k = 0; k < 4; k++) {
                const float f0 = (float)vx[k].x, f1 = (float)vx[k].y, f2 = (float)vx[k].z, f3 = (float)vx[k].w;
                acc0[0] = fmaf(w0[k], f0, acc0[0]); acc1[0] = fmaf(w1[k], f0, acc1[0]);
                acc0[1] = fmaf(w0[k], f1, acc0[1]); acc1[1] = fmaf(w1[k], f1, acc1[1]);
                acc0[2] = fmaf(w0[k], f2, acc0[2]); acc1[2] = fmaf(w1[k], f2, acc1[2]);
                acc0[3] = fmaf(w0[k], f3, acc0[3]); acc1[3] = fmaf(w1[k], f3, acc1[3]);
            }
        }
        if (nhead != head) {
            *reinterpret_cast<float4*>(&sm.wacc[abuf][warp][0][lane * 4]) = make_float4(acc0[0], acc0[1], acc0[2], acc0[3]);
            *reinterpret_cast<float4*>(&sm.wacc[abuf][warp][1][lane * 4]) = make_float4(acc1[0], acc1[1], acc1[2], acc1[3]);
            cons_sync();
            if (tid < REP * NCOL) {
                float2 a[CW];
#pragma unroll
                for (int i = 0; i < CW; i++) a[i] = *reinterpret_cast<const float2*>(&sm.wacc[abuf][i][0][tid * 2]);
#pragma unroll
                for (int o = CW / 2; o > 0; o >>= 1)
#pragma unroll
                    for (int i = 0; i < o; i++) { a[i].x += a[i + o].x; a[i].y += a[i + o].y; }
                st_relaxed_b128(&g_part[b][head * REP][tid], __float_as_uint(a[0].x), __float_as_uint(a[0].y),
                                __float_as_uint(tid < NCOL ? lse0 : lse1), tag);
#pragma unroll 1
                for (int h = head + 1; h < nhead; h++)
                    st_relaxed_b128(&g_part[b][h * REP][tid], 0u, 0u, 0xff800000u, tag);
                if (nhead == HKV - 1) st_relaxed_b128(&g_part[b][nhead * REP][tid], 0u, 0u, 0u, epoch);
            }
            abuf ^= 1;
#pragma unroll
            for (int i = 0; i < 4; i++) { acc0[i] = 0.f; acc1[i] = 0.f; }
        }
        __syncwarp();
        if (lane == 0) mbar_arrive(smem_u32(&sm.empty[s]));
        if (++s == NST) { s = 0; ph ^= 1; }
        t = tn;
    }
}

}

typedef CUresult (*kvq_encode_fn)(CUtensorMap*, CUtensorMapDataType, cuuint32_t, void*, const cuuint64_t*,
                                  const cuuint64_t*, const cuuint32_t*, const cuuint32_t*, CUtensorMapInterleave,
                                  CUtensorMapSwizzle, CUtensorMapL2promotion, CUtensorMapFloatOOBfill);

extern "C" void kernel_launch(void* const* d_in, const int* in_sizes, int n_in, void* d_out, int out_size) {
    (void)in_sizes; (void)n_in; (void)out_size;
    static int grid = 0;
    static kvq_encode_fn encode = nullptr;
    if (grid == 0) {
        int dev = 0, sms = 0;
        cudaGetDevice(&dev);
        cudaDeviceGetAttribute(&sms, cudaDevAttrMultiProcessorCount, dev);
        cudaFuncSetAttribute(kvq::decode_kernel, cudaFuncAttributeMaxDynamicSharedMemorySize, (int)sizeof(kvq::Smem));
        cudaDriverEntryPointQueryResult qres;
        cudaGetDriverEntryPoint("cuTensorMapEncodeTiled", (void**)&encode, cudaEnableDefault, &qres);
        grid = sms < kvq::MAXG ? sms : kvq::MAXG;
    }
    if (encode == nullptr) return;
    CUtensorMap vmap;
    const cuuint64_t dims[2] = {(cuuint64_t)kvq::DH, (cuuint64_t)kvq::HKV * kvq::SKV};
    const cuuint64_t strides[1] = {(cuuint64_t)kvq::DH * 4};
    const cuuint32_t box[2] = {(cuuint32_t)(kvq::DH / kvq::NSL), (cuuint32_t)kvq::SL_ROWS};
    const cuuint32_t estr[2] = {1, 1};
    encode(&vmap, CU_TENSOR_MAP_DATA_TYPE_INT32, 2, d_in[2], dims, strides, box, estr, CU_TENSOR_MAP_INTERLEAVE_NONE,
           CU_TENSOR_MAP_SWIZZLE_NONE, CU_TENSOR_MAP_L2_PROMOTION_L2_128B, CU_TENSOR_MAP_FLOAT_OOB_FILL_NONE);
    cudaLaunchConfig_t cfg = {};
    cfg.gridDim = dim3(grid);
    cfg.blockDim = dim3(kvq::NCT + 32);
    cfg.dynamicSmemBytes = sizeof(kvq::Smem);
    cfg.stream = cudaStreamPerThread;
    cudaLaunchAttribute attr[1];
    attr[0].id = cudaLaunchAttributeCooperative;
    attr[0].val.cooperative = 1;
    cfg.attrs = attr;
    cfg.numAttrs = 1;
    cudaLaunchKernelEx(&cfg, kvq::decode_kernel, (const uint16_t*)d_in[0], (const int*)d_in[1], (const int*)d_in[2],
                       (const uint16_t*)d_in[3], (const uint16_t*)d_in[4], (const uint16_t*)d_in[5],
                       (const uint16_t*)d_in[6], (__nv_bfloat16*)d_out, vmap);
}
```
